```python
import torch

def _softmax(x, axis=-1):
    return torch.softmax(x, dim=axis)
def _gelu(x):
    return torch.nn.functional.gelu(x, approximate="tanh")
def _silu(x):
    return torch.nn.functional.silu(x)
def _sigmoid(x):
    return torch.sigmoid(x)
def _layernorm(x, axis=-1, eps=1e-5):
    m = x.mean(dim=axis, keepdim=True)
    v = x.var(dim=axis, keepdim=True, unbiased=False)
    return (x - m) / torch.sqrt(v + eps)
def _scatter_add(tgt, idx, src, axis=0):
    return tgt.clone().index_add_(axis, idx, src)
def _segment_sum(src, seg, n):
    out = torch.zeros((n,) + src.shape[1:], dtype=src.dtype)
    return out.index_add_(0, seg, src)
def _pad(x, pw):
    flat = tuple(v for pair in reversed(pw) for v in pair)
    return torch.nn.functional.pad(x, flat)

kernel_name = 'parallel_sum__mha_block__moe_arch_mod__prompt'

def setup_inputs():

    _w = (lambda a: (lambda t: t.to(torch.bfloat16) if t.is_floating_point() else t)(torch.as_tensor(a)))
    def _A_setup():
        B, S, D, H = 1, 2048, 512, 32
        return {
            "x": _w((lambda *s: torch.randn(*s, dtype=torch.bfloat16) * 0.05)(B, S, D)),
            "wqkv": _w((lambda *s: torch.randn(*s, dtype=torch.bfloat16) * 0.2)(D, 3 * D)),
            "wo": _w((lambda *s: torch.randn(*s, dtype=torch.bfloat16) * 0.1)(D, D)),
        }
    _A_in = _A_setup()

    def _B_setup():
        B, S, D, F, C = 1, 2048, 512, 1792, 1
        return {
            "x": _w((lambda *s: torch.randn(*s, dtype=torch.bfloat16) * 0.05)(B, S, D)),
            "w_r": _w((lambda *s: torch.randn(*s, dtype=torch.bfloat16) * 1.6)(D)),
            "w_gate": _w((lambda *s: torch.randn(*s, dtype=torch.bfloat16) * 0.2)(D, F)),
            "w_up": _w((lambda *s: torch.randn(*s, dtype=torch.bfloat16) * 0.2)(D, F)),
            "w_down": _w((lambda *s: torch.randn(*s, dtype=torch.bfloat16) * 0.2)(F, D)),
        }
    _B_in = _B_setup()

    return {
        "A_x": _A_in["x"],
        "A_wqkv": _A_in["wqkv"],
        "A_wo": _A_in["wo"],
        "B_x": _B_in["x"],
        "B_w_r": _B_in["w_r"],
        "B_w_gate": _B_in["w_gate"],
        "B_w_up": _B_in["w_up"],
        "B_w_down": _B_in["w_down"],
    }

def reference(A_x, A_wqkv, A_wo, B_x, B_w_r, B_w_gate, B_w_up, B_w_down):
    def _A_ref(x, wqkv, wo):
        B, S, D = x.shape
        H = 32
        Dh = D // H
        qkv = (lambda x, *d: x.permute(*d))((x @ wqkv).reshape(B, S, 3, H, Dh), 2, 0, 3, 1, 4)
        q, k, v = qkv[0], qkv[1], qkv[2]
        scores = torch.einsum("bhqd,bhkd->bhqk", q, k) * (Dh ** -0.5)
        p = _softmax(scores, axis=-1)
        o = torch.einsum("bhqk,bhkd->bhqd", p, v)
        return (lambda x, *d: x.permute(*d))(o, 0, 2, 1, 3).reshape(B, S, D) @ wo

    def _B_ref(x, w_r, w_gate, w_up, w_down):
        B, S, D = x.shape
        C = 1
        r = x @ w_r
        idx = torch.argsort(-r, axis=-1)[:, :C]
        idx_e = (lambda x, n, axis: torch.repeat_interleave(x, n, dim=axis))(idx.reshape(B, C, 1), D, axis=2)
        x_sel = (lambda x, i, axis: torch.take_along_dim(x, i, dim=axis))(x, idx_e, axis=1)
        g = _silu(x_sel @ w_gate)
        u = x_sel @ w_up
        y = (g * u) @ w_down
        r_sel = _sigmoid((lambda x, i, axis: torch.take_along_dim(x, i, dim=axis))(r, idx, axis=1))
        y = y * r_sel.reshape(B, C, 1)
        b_off = (torch.arange(B) * S).reshape(B, 1)
        flat_idx = (idx + b_off).reshape(B * C)
        zero = (x * 0.0).reshape(B * S, D)
        upd = _scatter_add(zero, flat_idx, y.reshape(B * C, D), axis=0)
        return x + upd.reshape(B, S, D)

    x = A_x
    xn = _layernorm(x, axis=-1)
    return x + _A_ref(xn, A_wqkv, A_wo) + _B_ref(xn, B_w_r, B_w_gate, B_w_up, B_w_down)
```

```cpp
#include <cuda_runtime.h>
#include <cuda_bf16.h>
#include <cuda.h>
#include <stdint.h>

namespace {

constexpr int S_ = 2048, D_ = 512, F_ = 1792;
constexpr int NMAIN = 128, NMOE = 4, NCTA = NMAIN + NMOE;
constexpr int FS = F_ / NMOE;

constexpr int NTHR = 640;

constexpr int STAGE = 45056, BLK = 40960;
constexpr int SM_WO0 = 122880, SM_B0 = 155648, SM_WO1 = 196608, SM_BIAS = 229376, SM_BAR = 231424;
constexpr int SM_QX = SM_WO1;
constexpr int SM_ST = SM_WO1 + 8192, SM_CS = SM_ST + 2048, SM_P0S = SM_CS + 512;
constexpr int SM_WC = SM_WO1 + 16384;
constexpr int SM_RT = SM_BAR + 336;
constexpr int SM_TOTAL = SM_RT + 16 + 256;
constexpr int B_FULL = 0, B_CS = 3, B_REL = 4, B_KL = 7, B_KV = 8, B_WO = 12, B_QX = 13, B_EARLY = 14, B_O = 15, B_DONE = 23, B_STG = 31, B_QR = 32, B_SO = 33;
constexpr int NB_KV = 9, NB_DONE = 14;

constexpr int C_KV = 1, C_O = 129, C_MOE = 385, C_DONE = 386, NCNT = 387;

__device__ unsigned g_cnt[NCNT * 32];
__device__ uint4 g_KV[32 * 4 * 2048];
__device__ uint4 g_O[32 * 32 * 128];
__device__ uint2 g_stats[S_];
__device__ uint2 g_colsum[3 * D_];
__device__ uint2 g_best[NMAIN];
__device__ float g_ypart[NMOE * D_];
__device__ float2 g_route;

#define TS(i)
#define TSG(i)
#define TSV(i, v)
template<int SCALE_D> __device__ __forceinline__ void wgmma_n64_k(float (&d)[32], uint32_t a0, uint32_t a1, uint32_t a2, uint32_t a3, uint64_t db) {
  asm volatile("{\n.reg .pred p;\nsetp.ne.b32 p, %37, 0;\n"
    "wgmma.mma_async.sync.aligned.m64n64k16.f32.bf16.bf16 "
    "{%0, %1, %2, %3, %4, %5, %6, %7, %8, %9, %10, %11, %12, %13, %14, %15, %16, %17, %18, %19, %20, %21, %22, %23, %24, %25, %26, %27, %28, %29, %30, %31}, "
    "{%32, %33, %34, %35}, %36, p, 1, 1, 0;\n}\n"
    : "+f"(d[0]), "+f"(d[1]), "+f"(d[2]), "+f"(d[3]), "+f"(d[4]), "+f"(d[5]), "+f"(d[6]), "+f"(d[7]),
      "+f"(d[8]), "+f"(d[9]), "+f"(d[10]), "+f"(d[11]), "+f"(d[12]), "+f"(d[13]), "+f"(d[14]), "+f"(d[15]),
      "+f"(d[16]), "+f"(d[17]), "+f"(d[18]), "+f"(d[19]), "+f"(d[20]), "+f"(d[21]), "+f"(d[22]), "+f"(d[23]),
      "+f"(d[24]), "+f"(d[25]), "+f"(d[26]), "+f"(d[27]), "+f"(d[28]), "+f"(d[29]), "+f"(d[30]), "+f"(d[31])
    : "r"(a0), "r"(a1), "r"(a2), "r"(a3), "l"(db), "n"(SCALE_D));
}
template<int SCALE_D> __device__ __forceinline__ void wgmma_n24_t(float (&d)[12], uint32_t a0, uint32_t a1, uint32_t a2, uint32_t a3, uint64_t db) {
  asm volatile("{\n.reg .pred p;\nsetp.ne.b32 p, %17, 0;\n"
    "wgmma.mma_async.sync.aligned.m64n24k16.f32.bf16.bf16 "
    "{%0, %1, %2, %3, %4, %5, %6, %7, %8, %9, %10, %11}, "
    "{%12, %13, %14, %15}, %16, p, 1, 1, 1;\n}\n"
    : "+f"(d[0]), "+f"(d[1]), "+f"(d[2]), "+f"(d[3]), "+f"(d[4]), "+f"(d[5]), "+f"(d[6]), "+f"(d[7]),
      "+f"(d[8]), "+f"(d[9]), "+f"(d[10]), "+f"(d[11])
    : "r"(a0), "r"(a1), "r"(a2), "r"(a3), "l"(db), "n"(SCALE_D));
}
template<int SCALE_D> __device__ __forceinline__ void wgmma_n96_ss_t(float (&d)[48], uint64_t da, uint64_t db) {
  asm volatile("{\n.reg .pred p;\nsetp.ne.b32 p, %50, 0;\n"
    "wgmma.mma_async.sync.aligned.m64n96k16.f32.bf16.bf16 "
    "{%0, %1, %2, %3, %4, %5, %6, %7, %8, %9, %10, %11, %12, %13, %14, %15, %16, %17, %18, %19, %20, %21, %22, %23, %24, %25, %26, %27, %28, %29, %30, %31, %32, %33, %34, %35, %36, %37, %38, %39, %40, %41, %42, %43, %44, %45, %46, %47}, "
    "%48, %49, p, 1, 1, 0, 1;\n}\n"
    : "+f"(d[0]), "+f"(d[1]), "+f"(d[2]), "+f"(d[3]), "+f"(d[4]), "+f"(d[5]), "+f"(d[6]), "+f"(d[7]),
      "+f"(d[8]), "+f"(d[9]), "+f"(d[10]), "+f"(d[11]), "+f"(d[12]), "+f"(d[13]), "+f"(d[14]), "+f"(d[15]),
      "+f"(d[16]), "+f"(d[17]), "+f"(d[18]), "+f"(d[19]), "+f"(d[20]), "+f"(d[21]), "+f"(d[22]), "+f"(d[23]),
      "+f"(d[24]), "+f"(d[25]), "+f"(d[26]), "+f"(d[27]), "+f"(d[28]), "+f"(d[29]), "+f"(d[30]), "+f"(d[31]),
      "+f"(d[32]), "+f"(d[33]), "+f"(d[34]), "+f"(d[35]), "+f"(d[36]), "+f"(d[37]), "+f"(d[38]), "+f"(d[39]),
      "+f"(d[40]), "+f"(d[41]), "+f"(d[42]), "+f"(d[43]), "+f"(d[44]), "+f"(d[45]), "+f"(d[46]), "+f"(d[47])
    : "l"(da), "l"(db), "n"(SCALE_D));
}
template<int SCALE_D> __device__ __forceinline__ void wgmma_n64_t(float (&d)[32], uint32_t a0, uint32_t a1, uint32_t a2, uint32_t a3, uint64_t db) {
  asm volatile("{\n.reg .pred p;\nsetp.ne.b32 p, %37, 0;\n"
    "wgmma.mma_async.sync.aligned.m64n64k16.f32.bf16.bf16 "
    "{%0, %1, %2, %3, %4, %5, %6, %7, %8, %9, %10, %11, %12, %13, %14, %15, %16, %17, %18, %19, %20, %21, %22, %23, %24, %25, %26, %27, %28, %29, %30, %31}, "
    "{%32, %33, %34, %35}, %36, p, 1, 1, 1;\n}\n"
    : "+f"(d[0]), "+f"(d[1]), "+f"(d[2]), "+f"(d[3]), "+f"(d[4]), "+f"(d[5]), "+f"(d[6]), "+f"(d[7]),
      "+f"(d[8]), "+f"(d[9]), "+f"(d[10]), "+f"(d[11]), "+f"(d[12]), "+f"(d[13]), "+f"(d[14]), "+f"(d[15]),
      "+f"(d[16]), "+f"(d[17]), "+f"(d[18]), "+f"(d[19]), "+f"(d[20]), "+f"(d[21]), "+f"(d[22]), "+f"(d[23]),
      "+f"(d[24]), "+f"(d[25]), "+f"(d[26]), "+f"(d[27]), "+f"(d[28]), "+f"(d[29]), "+f"(d[30]), "+f"(d[31])
    : "r"(a0), "r"(a1), "r"(a2), "r"(a3), "l"(db), "n"(SCALE_D));
}
__device__ __forceinline__ void wg_fence() { asm volatile("wgmma.fence.sync.aligned;" ::: "memory"); }
__device__ __forceinline__ void wg_commit() { asm volatile("wgmma.commit_group.sync.aligned;" ::: "memory"); }
template <int N> __device__ __forceinline__ void wg_wait() { asm volatile("wgmma.wait_group.sync.aligned %0;" ::"n"(N) : "memory"); }
template <int N> __device__ __forceinline__ void pin(float (&d)[N]) {
#pragma unroll
  for (int i = 0; i < N; i++) asm volatile("" : "+f"(d[i])::"memory");
}
__device__ __forceinline__ uint64_t mkdesc(uint32_t addr, uint32_t lbo, uint32_t sbo, uint64_t swz = 0) {
  return (uint64_t)((addr & 0x3FFFF) >> 4) | ((uint64_t)(lbo >> 4) << 16) | ((uint64_t)(sbo >> 4) << 32) | (swz << 62);
}
__device__ __forceinline__ void fence_async() { asm volatile("fence.proxy.async.shared::cta;" ::: "memory"); }
__device__ __forceinline__ void fence_async_g() { asm volatile("fence.proxy.async.global;" ::: "memory"); }
__device__ __forceinline__ void cp16(uint32_t dst, const void* src) {
  asm volatile("cp.async.cg.shared.global [%0], [%1], 16;" ::"r"(dst), "l"(src) : "memory");
}
__device__ __forceinline__ void cp_commit() { asm volatile("cp.async.commit_group;" ::: "memory"); }
template <int N> __device__ __forceinline__ void cp_wait() { asm volatile("cp.async.wait_group %0;" ::"n"(N) : "memory"); }
__device__ __forceinline__ void mbar_init(uint32_t bar, int cnt) { asm volatile("mbarrier.init.shared::cta.b64 [%0], %1;" ::"r"(bar), "r"(cnt) : "memory"); }
__device__ __forceinline__ void mbar_expect(uint32_t bar, uint32_t bytes) {
  asm volatile("mbarrier.arrive.expect_tx.shared::cta.b64 _, [%0], %1;" ::"r"(bar), "r"(bytes) : "memory");
}
__device__ __forceinline__ void mbar_wait(uint32_t bar, uint32_t parity = 0) {
  for (int i = 0; i < (1 << 15); i++) {
    uint32_t ok;
    asm volatile("{\n.reg .pred p;\nmbarrier.try_wait.parity.shared::cta.b64 p, [%1], %2;\nselp.b32 %0, 1, 0, p;\n}" : "=r"(ok) : "r"(bar), "r"(parity) : "memory");
    if (ok) break;
  }
}
__device__ __forceinline__ void bulk_g2s(uint32_t dst, const void* src, uint32_t bytes, uint32_t bar) {
  asm volatile("cp.async.bulk.shared::cluster.global.mbarrier::complete_tx::bytes [%0], [%1], %2, [%3];" ::"r"(dst), "l"(src), "r"(bytes), "r"(bar) : "memory");
}
__device__ __forceinline__ void tma2(uint32_t dst, const CUtensorMap* m, int c0, int c1, uint32_t bar) {
  asm volatile("cp.async.bulk.tensor.2d.shared::cluster.global.mbarrier::complete_tx::bytes [%0], [%1, {%3, %4}], [%2];" ::"r"(dst), "l"(m), "r"(bar), "r"(c0), "r"(c1) : "memory");
}
__device__ __forceinline__ void tma3(uint32_t dst, const CUtensorMap* m, int c0, int c1, int c2, uint32_t bar) {
  asm volatile("cp.async.bulk.tensor.3d.shared::cluster.global.mbarrier::complete_tx::bytes [%0], [%1, {%3, %4, %5}], [%2];" ::"r"(dst), "l"(m), "r"(bar), "r"(c0), "r"(c1), "r"(c2) : "memory");
}
__device__ __forceinline__ void mbar_arrive(uint32_t bar) { asm volatile("mbarrier.arrive.shared::cta.b64 _, [%0];" ::"r"(bar) : "memory"); }
__device__ __forceinline__ void mbar_wait_cl(uint32_t bar) {
  for (int i = 0; i < (1 << 15); i++) {
    uint32_t ok;
    asm volatile("{\n.reg .pred p;\nmbarrier.try_wait.parity.acquire.cluster.shared::cta.b64 p, [%1], 0;\nselp.b32 %0, 1, 0, p;\n}" : "=r"(ok) : "r"(bar) : "memory");
    if (ok) break;
  }
}
__device__ __forceinline__ uint32_t mapa(uint32_t addr, uint32_t rank) {
  uint32_t r;
  asm("mapa.shared::cluster.u32 %0, %1, %2;" : "=r"(r) : "r"(addr), "r"(rank));
  return r;
}
__device__ __forceinline__ void st_async4(uint32_t addr, const uint32_t* v, uint32_t bar) {
  asm volatile("st.async.weak.shared::cluster.mbarrier::complete_tx::bytes.v4.b32 [%0], {%1, %2, %3, %4}, [%5];"
               ::"r"(addr), "r"(v[0]), "r"(v[1]), "r"(v[2]), "r"(v[3]), "r"(bar) : "memory");
}
__device__ __forceinline__ void st_async(uint32_t addr, uint32_t v, uint32_t bar) {
  asm volatile("st.async.weak.shared::cluster.mbarrier::complete_tx::bytes.b32 [%0], %1, [%2];" ::"r"(addr), "r"(v), "r"(bar) : "memory");
}
__device__ __forceinline__ void stsm4(uint32_t addr, const uint32_t* r) {
  asm volatile("stmatrix.sync.aligned.m8n8.x4.shared.b16 [%0], {%1, %2, %3, %4};" ::"r"(addr), "r"(r[0]), "r"(r[1]), "r"(r[2]), "r"(r[3]) : "memory");
}
__device__ __forceinline__ void quad_transpose(uint32_t* v, int t) {
#pragma unroll
  for (int st = 1; st < 4; st <<= 1) {
    const bool up = t & st;
#pragma unroll
    for (int b = 0; b < 4; b++) {
      if (b & st) continue;
      const uint32_t r = __shfl_xor_sync(0xffffffffu, up ? v[b] : v[b + st], st);
      if (up) v[b] = r; else v[b + st] = r;
    }
  }
}
__device__ __forceinline__ void cnt_arrive(int c) {
  asm volatile("fence.release.gpu;\nred.relaxed.gpu.global.add.u32 [%0], 1;" ::"l"(&g_cnt[c * 32]) : "memory");
}
__device__ __forceinline__ void cnt_wait(int c, unsigned ep, unsigned n) {
  const unsigned target = (ep + 1) * n;
#pragma unroll 1
  for (int i = 0; i < (1 << 17); i++) {
    unsigned v;
    asm volatile("ld.relaxed.gpu.global.u32 %0, [%1];" : "=r"(v) : "l"(&g_cnt[c * 32]) : "memory");
    if ((int)(v - target) >= 0) break;
  }
  asm volatile("fence.acquire.gpu;" ::: "memory");
}
__device__ __forceinline__ void bar_pair(int pair) { asm volatile("bar.sync %0, 256;" ::"r"(pair + 5) : "memory"); }
template <int ID, int N> __device__ __forceinline__ void bar_sync() { asm volatile("bar.sync %0, %1;" ::"n"(ID), "n"(N) : "memory"); }
template <int ID, int N> __device__ __forceinline__ void bar_arrive() { asm volatile("bar.arrive %0, %1;" ::"n"(ID), "n"(N) : "memory"); }
__device__ __forceinline__ bool wg_any(int wg, bool v) {
  uint32_t r;
  asm volatile("{\n.reg .pred p, q;\nsetp.ne.b32 p, %1, 0;\nbar.red.or.pred q, %2, 128, p;\nselp.b32 %0, 1, 0, q;\n}" : "=r"(r) : "r"((uint32_t)v), "r"(wg + 1) : "memory");
  return r != 0;
}
__device__ __forceinline__ uint32_t packbf(float lo, float hi) {
  uint32_t r;
  asm("cvt.rn.bf16x2.f32 %0, %1, %2;" : "=r"(r) : "f"(hi), "f"(lo));
  return r;
}
__device__ __forceinline__ float bflo(uint32_t v) { return __uint_as_float(v << 16); }
__device__ __forceinline__ float bfhi(uint32_t v) { return __uint_as_float(v & 0xFFFF0000u); }
__device__ __forceinline__ float rbf(float x) { return bflo(packbf(x, x)); }
__device__ __forceinline__ float rcp(float x) {
  float y;
  asm("rcp.approx.ftz.f32 %0, %1;" : "=f"(y) : "f"(x));
  return y;
}
__device__ __forceinline__ float ex2(float x) {
  float y;
  asm("ex2.approx.ftz.f32 %0, %1;" : "=f"(y) : "f"(x));
  return y;
}
__device__ __forceinline__ uint4 ldg_cg(const void* p) {
  uint4 v;
  asm volatile("ld.global.cg.v4.u32 {%0,%1,%2,%3}, [%4];" : "=r"(v.x), "=r"(v.y), "=r"(v.z), "=r"(v.w) : "l"(p) : "memory");
  return v;
}
__device__ __forceinline__ void unpack8(const uint4& v, float* f) {
  f[0] = bflo(v.x); f[1] = bfhi(v.x); f[2] = bflo(v.y); f[3] = bfhi(v.y);
  f[4] = bflo(v.z); f[5] = bfhi(v.z); f[6] = bflo(v.w); f[7] = bfhi(v.w);
}
template <int N, int DIST> __device__ __forceinline__ void fold_step(float* c, int lane) {
  const bool up = lane & DIST;
#pragma unroll
  for (int i = 0; i < N; i++) {
    const float send = up ? c[i] : c[i + N], keep = up ? c[i + N] : c[i];
    c[i] = keep + __shfl_xor_sync(0xffffffffu, send, DIST);
  }
}
__device__ __forceinline__ float ln_elem(float x, float mean, float rsd) { return rbf(rbf(x - mean) * rsd); }

constexpr float TWO_P71 = 2361183241434822606848.0f;
constexpr float TWO_M71 = 1.0f / 2361183241434822606848.0f;
constexpr float QSCALE = 0.25f * 1.4426950408889634f;
constexpr float M_SHIFT = 96.0f;
constexpr float FIX_M = 126.4176f;

#define MU_MASK 0x14
__host__ __device__ constexpr bool is_mu(int kg) { return (MU_MASK >> (kg & 7)) & 1; }

template <bool ALT> __device__ __forceinline__ uint32_t exp2_fx_pair(float t0, float t1, uint32_t hexp, uint32_t neg1) {
  uint32_t v, h, r;
  asm("cvt.pack.sat.s16.s32 %0, %1, %2;" : "=r"(v) : "r"(__float_as_uint(t1)), "r"(__float_as_uint(t0)));
  const uint32_t e = v & 0xFF80FF80u;
  if (ALT) {
    asm("mad.lo.u32 %0, %1, %2, %3;" : "=r"(h) : "r"(e), "r"(neg1), "r"(v));
    asm("add.u16x2 %0, %0, %1;" : "+r"(h) : "r"(hexp));
  } else {
    asm("lop3.b32 %0, %1, 0x007F007F, %2, 0xEA;" : "=r"(h) : "r"(v), "r"(hexp));
  }
  asm("fma.rn.bf16x2 %0, %1, %2, %3;" : "=r"(r) : "r"(v), "r"(h), "r"(e));
  return r;
}
#define EPRE 8
#define EO 0
#define DINV 0
#define ALT_MASK 0x0401

__device__ __forceinline__ uint32_t blk_off(int b) { return b == 0 ? SM_B0 : (b - 1) * BLK; }
struct Attn {
  float s[32];
  uint32_t p[2][16];
  float o[12];
  uint32_t q[4];
  uint32_t hexp, neg1;
  template <bool FIX, int B, int blk> __device__ __forceinline__ void make_p() {
    if constexpr (blk < 8) {
      constexpr int i = blk * 4;
      if constexpr (is_mu(blk)) {
        constexpr float moff = FIX ? FIX_M : 0.f;
        p[B][2 * blk] = packbf(ex2(s[i] - moff), ex2(s[i + 1] - moff));
        p[B][2 * blk + 1] = packbf(ex2(s[i + 2] - moff), ex2(s[i + 3] - moff));
      } else {
        p[B][2 * blk] = exp2_fx_pair<(ALT_MASK >> (2 * blk)) & 1>(s[i], s[i + 1], hexp, neg1);
        p[B][2 * blk + 1] = exp2_fx_pair<(ALT_MASK >> (2 * blk + 1)) & 1>(s[i + 2], s[i + 3], hexp, neg1);
      }
      make_p<FIX, B, blk + 1>();
    }
  }
  template <int U, int u, bool DRAIN = true> __device__ __forceinline__ void steps(uint64_t k0, uint64_t v0, uint64_t knext) {
    if constexpr (u < U) {
      constexpr int B = u & 1;
      make_p<true, B, 0>();
      wg_fence();
      wgmma_n64_k<0>(s, q[0], q[1], q[2], q[3], u == U - 1 ? knext : k0 + (u + 1) * 128);
      wg_commit();
#pragma unroll
      for (int c = 0; c < 4; c++) wgmma_n24_t<1>(o, p[B][4 * c], p[B][4 * c + 1], p[B][4 * c + 2], p[B][4 * c + 3], v0 + u * 64 + c * 16);
      wg_commit();
      if constexpr (u == 7 && DRAIN) { wg_wait<0>(); pin(o); } else wg_wait<1>();
      pin(s);
      steps<U, u + 1, DRAIN>(k0, v0, knext);
    }
  }
  __device__ __forceinline__ void run(uint64_t dK, uint64_t dV, uint32_t bars) {
    steps<7, 0>(dK + (SM_B0 >> 4), dV + (SM_B0 >> 4), dK + (SM_B0 >> 4) + 7 * 128);
    mbar_wait(bars + (B_KV + 1) * 8);
    steps<8, 7, false>(dK + (SM_B0 >> 4), dV + (SM_B0 >> 4), dK);
    steps<7, 0>(dK, dV, dK + 7 * 128);
    mbar_wait(bars + (B_KV + 2) * 8);
    steps<8, 7, false>(dK, dV, dK + (BLK >> 4));
    steps<7, 0>(dK + (BLK >> 4), dV + (BLK >> 4), dK + (BLK >> 4) + 7 * 128);
    mbar_wait(bars + (B_KV + 3) * 8);
    steps<8, 7, false>(dK + (BLK >> 4), dV + (BLK >> 4), dK + 2 * (BLK >> 4));
    steps<8, 0>(dK + 2 * (BLK >> 4), dV + 2 * (BLK >> 4), dK);
  }
  template <int B> __device__ __forceinline__ void step_rowm(uint64_t kn, uint64_t v0, const uint32_t (&bq)[4], uint64_t dbias) {
    make_p<false, B, 0>();
    wg_fence();
    wgmma_n64_k<0>(s, bq[0], bq[1], bq[2], bq[3], dbias);
    wgmma_n64_k<1>(s, q[0], q[1], q[2], q[3], kn);
    wg_commit();
#pragma unroll
    for (int c = 0; c < 4; c++) wgmma_n24_t<1>(o, p[B][4 * c], p[B][4 * c + 1], p[B][4 * c + 2], p[B][4 * c + 3], v0 + c * 16);
    wg_commit();
    if (B) { wg_wait<0>(); pin(o); } else wg_wait<1>();
    pin(s);
  }
  __device__ __forceinline__ void run_rowm(uint64_t dK, uint64_t dV, uint32_t bars, const uint32_t (&bq)[4], uint64_t dbias) {
    wg_fence();
    wgmma_n64_k<1>(s, bq[0], bq[1], bq[2], bq[3], dbias);
    wg_commit();
    wg_wait<0>();
    pin(s);
#pragma unroll 1
    for (int tl = 0; tl < 32; tl += 2) {
      const int tn = (tl + 2) & 31;
      const uint64_t off = blk_off(tl >> 3) >> 4;
      step_rowm<0>(dK + off + ((tl & 7) + 1) * 128, dV + off + (tl & 7) * 64, bq, dbias);
      if ((tn & 7) == 0) mbar_wait(bars + (B_KV + (tn >> 3)) * 8);
      step_rowm<1>(dK + (blk_off(tn >> 3) >> 4) + (tn & 7) * 128, dV + off + (tl & 7) * 64 + 64, bq, dbias);
    }
  }
};

__device__ __forceinline__ void ll_put(uint2* p, uint32_t v, unsigned ep) {
  asm volatile("st.relaxed.gpu.global.v2.u32 [%0], {%1, %2};" ::"l"(p), "r"(v), "r"(ep + 1) : "memory");
}
__device__ __forceinline__ uint32_t ll_get(const uint2* p, unsigned ep) {
  uint32_t v, tag;
#pragma unroll 1
  for (int i = 0; i < (1 << 17); i++) {
    asm volatile("ld.relaxed.gpu.global.v2.u32 {%0, %1}, [%2];" : "=r"(v), "=r"(tag) : "l"(p) : "memory");
    if (tag == ep + 1) break;
  }
  return v;
}
__device__ __forceinline__ float2 unpack_stats(uint32_t v) { return make_float2(bflo(v), rcp(bfhi(v))); }

struct Params {
  const __nv_bfloat16 *x, *wr, *wg, *wu, *wd;
  __nv_bfloat16* out;
  uint64_t pad[2];
  CUtensorMap mx, mw, mc, mo;
};
__device__ __forceinline__ unsigned launch_epoch() {
  unsigned v;
  asm volatile("ld.relaxed.gpu.global.u32 %0, [%1];" : "=r"(v) : "l"(&g_cnt[C_DONE * 32]) : "memory");
  return v / NCTA;
}
__device__ __forceinline__ void epoch_done() { asm volatile("red.relaxed.gpu.global.add.u32 [%0], 1;" ::"l"(&g_cnt[C_DONE * 32]) : "memory"); }
__device__ __forceinline__ int fresh_tid() {
  int v;
  asm volatile("mov.u32 %0, %%tid.x;" : "=r"(v));
  return v;
}

__device__ __forceinline__ void moe_cta(const Params& P, uint8_t* smem, int s) {
  const int tid = threadIdx.x, lane = tid & 31, warp = tid >> 5;
  const uint32_t sb = (uint32_t)__cvta_generic_to_shared(smem);
  constexpr int STG = 57344, OFF = 3 * STG;
  float* xs = (float*)(smem + OFF);
  float* part = (float*)(smem + OFF + 2048);
  float* hs = (float*)(smem + OFF + 2048 + 28672);
  uint32_t* bs = (uint32_t*)(smem + OFF + 2048 + 28672 + 2048);
  const int cg = tid % 56, ks = tid / 56;
  const __nv_bfloat16* pg = P.wg + (size_t)(ks * 64) * F_ + s * FS + cg * 8;
  const __nv_bfloat16* pu = P.wu + (size_t)(ks * 64) * F_ + s * FS + cg * 8;
  auto issue_gu = [&](int st) {
    if (tid < FS && st < 16) {
#pragma unroll
      for (int k = 0; k < 4; k++) {
        cp16(sb + (st % 3) * STG + ((2 * k) * FS + tid) * 16, pg + (size_t)(st * 4 + k) * F_);
        cp16(sb + (st % 3) * STG + ((2 * k + 1) * FS + tid) * 16, pu + (size_t)(st * 4 + k) * F_);
      }
    }
    cp_commit();
  };
  issue_gu(0); issue_gu(1);
  const unsigned ep = launch_epoch();
  if (tid < NMAIN) {
    uint32_t bk = ll_get(&g_best[tid], ep);
#pragma unroll
    for (int o = 16; o > 0; o >>= 1) bk = max(bk, __shfl_xor_sync(0xffffffffu, bk, o));
    if (lane == 0) bs[warp] = bk;
  }
  bar_sync<1, 512>();
  TS(1);
  const uint32_t best = max(max(bs[0], bs[1]), max(bs[2], bs[3]));
  const int idx = ~best & (S_ - 1);
  {
    const float2 st = unpack_stats(ll_get(&g_stats[idx], ep));
    xs[tid] = ln_elem(__bfloat162float(P.x[idx * D_ + tid]), st.x, st.y);
    if (s == 0 && tid == 0) {
      const uint32_t u = ((best & 0x80000000u) ? (best ^ 0x80000000u) : ~best) & 0xFFFF0000u;
      g_route = make_float2(__int_as_float(idx), rbf(__frcp_rn(1.0f + __expf(-__uint_as_float(u)))));
    }
  }
  bar_sync<1, 512>();
  {
    float ag[8], au[8];
#pragma unroll
    for (int i = 0; i < 8; i++) ag[i] = au[i] = 0.f;
#pragma unroll 1
    for (int st = 0; st < 16; st++) {
      issue_gu(st + 2);
      cp_wait<2>();
      if (tid < FS) {
#pragma unroll
        for (int k = 0; k < 4; k++) {
          const float xv = xs[ks * 64 + st * 4 + k];
          float f[8];
          unpack8(*(const uint4*)(smem + (st % 3) * STG + ((2 * k) * FS + tid) * 16), f);
#pragma unroll
          for (int i = 0; i < 8; i++) ag[i] = fmaf(xv, f[i], ag[i]);
          unpack8(*(const uint4*)(smem + (st % 3) * STG + ((2 * k + 1) * FS + tid) * 16), f);
#pragma unroll
          for (int i = 0; i < 8; i++) au[i] = fmaf(xv, f[i], au[i]);
        }
      }
    }
    if (tid < FS) {
#pragma unroll
      for (int i = 0; i < 8; i++) { part[ks * FS + cg * 8 + i] = ag[i]; part[8 * FS + ks * FS + cg * 8 + i] = au[i]; }
    }
  }
  bar_sync<1, 512>();
  const int cd = tid & 63, rs = tid >> 6;
  const __nv_bfloat16* pd = P.wd + (size_t)(s * FS + rs * 56) * D_ + cd * 8;
  auto issue_d = [&](int st) {
    if (st < 8) {
#pragma unroll
      for (int k = 0; k < 7; k++) cp16(sb + (st % 3) * STG + (k * 512 + tid) * 16, pd + (size_t)(st * 7 + k) * D_);
    }
    cp_commit();
  };
  issue_d(0); issue_d(1);
  if (tid < FS) {
    float g = 0.f, u = 0.f;
#pragma unroll
    for (int k = 0; k < 8; k++) { g += part[k * FS + tid]; u += part[8 * FS + k * FS + tid]; }
    g = rbf(g); u = rbf(u);
    float sg = rbf(g * __frcp_rn(1.0f + __expf(-g)));
    hs[tid] = rbf(sg * u);
  }
  bar_sync<1, 512>();
  {
    float a8[8];
#pragma unroll
    for (int i = 0; i < 8; i++) a8[i] = 0.f;
#pragma unroll 1
    for (int st = 0; st < 8; st++) {
      issue_d(st + 2);
      cp_wait<2>();
#pragma unroll
      for (int k = 0; k < 7; k++) {
        const float hv = hs[rs * 56 + st * 7 + k];
        float f[8];
        unpack8(*(const uint4*)(smem + (st % 3) * STG + (k * 512 + tid) * 16), f);
#pragma unroll
        for (int i = 0; i < 8; i++) a8[i] = fmaf(hv, f[i], a8[i]);
      }
    }
#pragma unroll
    for (int i = 0; i < 8; i++) part[rs * D_ + cd * 8 + i] = a8[i];
  }
  bar_sync<1, 512>();
  {
    float y = 0.f;
#pragma unroll
    for (int k = 0; k < 8; k++) y += part[k * D_ + tid];
    g_ypart[s * D_ + tid] = y;
  }
  bar_sync<1, 512>();
  if (tid == 0) { cnt_arrive(C_MOE); epoch_done(); }
}

__device__ __forceinline__ void load_stage(const Params& P, uint32_t sb, int cta, int c, int slot) {
  const uint32_t bar = sb + SM_BAR + (B_FULL + slot) * 8, dst = sb + slot * STAGE;
  mbar_expect(bar, STAGE);
  tma2(dst, &P.mx, c * 64, (cta & 7) * 256, bar);
  tma3(dst + 32768, &P.mw, (cta >> 3) * 32, c * 64, 0, bar);
}

__device__ __forceinline__ void helper_wg(const Params& P, uint8_t* smem, int cta) {
  const int l = threadIdx.x - 512, lane = l & 31, hw = l >> 5;
  const uint32_t sb = (uint32_t)__cvta_generic_to_shared(smem), bars = sb + SM_BAR;
  const int jp = cta >> 3;
  unsigned tick;
  asm volatile("ld.relaxed.gpu.global.u32 %0, [%1];" : "=r"(tick) : "l"(&g_cnt[C_DONE * 32]) : "memory");
  bar_sync<0, NTHR>();
  asm volatile("barrier.cluster.arrive.relaxed.aligned;" ::: "memory");
  const __nv_bfloat16* xrow = P.x + (cta * 16 + hw * 4) * D_ + lane * 8;
  uint4 xr[4][2], wr2[2];
#pragma unroll
  for (int rr = 0; rr < 4; rr++) { xr[rr][0] = ldg_cg(xrow + rr * D_); xr[rr][1] = ldg_cg(xrow + rr * D_ + 256); }
  wr2[0] = ldg_cg(P.wr + lane * 8); wr2[1] = ldg_cg(P.wr + 256 + lane * 8);
  asm volatile("" : "+r"(tick));
  const unsigned ep = tick / NCTA;
  {
    float wv[16], mb[4] = {}, c[16] = {};
    unpack8(wr2[0], &wv[0]); unpack8(wr2[1], &wv[8]);
    float ws = 0.f;
#pragma unroll
    for (int i = 0; i < 16; i++) ws += wv[i];
#pragma unroll 1
    for (int rr = 0; rr < 4; rr++) {
      float v[16];
      unpack8(xr[0][0], &v[0]); unpack8(xr[0][1], &v[8]);
      const float sh = __shfl_sync(0xffffffffu, v[0], 0);
      float s1 = 0.f, s2 = 0.f, s3 = 0.f;
#pragma unroll
      for (int i = 0; i < 16; i++) { const float d = v[i] - sh; s1 += d; s2 = fmaf(d, d, s2); s3 = fmaf(d, wv[i], s3); }
#pragma unroll
      for (int i = 0; i < 3; i++) {
        xr[i][0] = xr[i + 1][0]; xr[i][1] = xr[i + 1][1];
        mb[i] = mb[i + 1]; c[i] = c[i + 1]; c[4 + i] = c[5 + i]; c[8 + i] = c[9 + i];
      }
      mb[3] = sh; c[3] = s1; c[7] = s2; c[11] = s3;
    }
    c[12] = c[13] = c[14] = c[15] = ws;
    TS(18);
    fold_step<8, 16>(c, lane); fold_step<4, 8>(c, lane); fold_step<2, 4>(c, lane); fold_step<1, 2>(c, lane);
    c[0] += __shfl_xor_sync(0xffffffffu, c[0], 1);
    const float sq = __shfl_xor_sync(0xffffffffu, c[0], 8), dot = __shfl_xor_sync(0xffffffffu, c[0], 16), wsum = __shfl_xor_sync(0xffffffffu, c[0], 24);
    const int rr = (lane >> 1) & 3;
    const float c0 = rr == 0 ? mb[0] : rr == 1 ? mb[1] : rr == 2 ? mb[2] : mb[3];
    const float md = c[0] * (1.0f / D_), m = rbf(c0 + md);
    const float sd = rbf(__fsqrt_rn(rbf(rbf(fmaxf(fmaf(-md, md, sq * (1.0f / D_)), 0.f)) + 1e-5f)));
    if (lane < 8 && (lane & 1) == 0) {
      const int row = cta * 16 + hw * 4 + rr;
      ll_put(&g_stats[row], packbf(m, sd), ep);
      const uint32_t ub = __float_as_uint(rbf(fmaf(c0 - m, wsum, dot) * rcp(sd)));
      ((uint32_t*)(smem + SM_P0S + 256))[hw * 4 + rr] = (((ub & 0x80000000u) ? ~ub : (ub | 0x80000000u)) & 0xFFFF0000u) | (~row & 0xFFFF);
    }
  }
  TS(19);
  {
    mbar_wait(bars + B_CS * 8);
    float c[16];
#pragma unroll
    for (int i = 0; i < 16; i++) c[i] = 0.f;
#pragma unroll
    for (int k = 0; k < 4; k++) {
      float f[16];
      const uint8_t* src = smem + SM_WC + (k * 128 + l) * 32;
      unpack8(*(const uint4*)src, &f[0]); unpack8(*(const uint4*)(src + 16), &f[8]);
#pragma unroll
      for (int i = 0; i < 16; i++) c[i] += f[i];
    }
    fold_step<8, 16>(c, lane); fold_step<4, 8>(c, lane); fold_step<2, 4>(c, lane); fold_step<1, 2>(c, lane);
    c[0] += __shfl_xor_sync(0xffffffffu, c[0], 1);
    if ((lane & 1) == 0) ((float*)(smem + SM_P0S))[hw * 16 + (lane >> 1)] = c[0];
  }
  TS(20);
  if (l == 0) *(volatile unsigned*)(smem + SM_RT + 4) = ep;
  asm volatile("setmaxnreg.dec.sync.aligned.u32 32;");
  bar_sync<8, 128>();
  if (hw == 1) {
    const float* p0cs = (const float*)(smem + SM_P0S);
    if (lane < 16 && cta < 96) ll_put(&g_colsum[cta * 16 + lane], __float_as_uint((p0cs[lane] + p0cs[16 + lane]) + (p0cs[32 + lane] + p0cs[48 + lane])), ep);
    uint32_t bk = ((const uint32_t*)(smem + SM_P0S + 256))[lane & 15];
#pragma unroll
    for (int o = 8; o > 0; o >>= 1) bk = max(bk, __shfl_xor_sync(0xffffffffu, bk, o));
    if (lane == 0) { ll_put(&g_best[cta], bk, ep); epoch_done(); }
  }
#pragma unroll
  for (int i = 0; i < 2; i++) ((float2*)(smem + SM_ST))[i * 128 + l] = unpack_stats(ll_get(&g_stats[(cta & 7) * 256 + i * 128 + l], ep));
  if (l < 96) ((uint32_t*)(smem + SM_CS))[l] = ll_get(&g_colsum[hw * D_ + jp * 32 + lane], ep);
  __syncwarp();
  if (lane == 0) mbar_arrive(bars + B_STG * 8);
  asm volatile("barrier.cluster.wait.aligned;" ::: "memory");
  __syncwarp();
  TS(1);
}

__device__ __forceinline__ void helper_wg2(const Params& P, uint8_t* smem, int cta) {
  const int l = fresh_tid() - 512, lane = l & 31, hw = l >> 5;
  const uint32_t sb = (uint32_t)__cvta_generic_to_shared(smem), bars = sb + SM_BAR;
  const int rank = cta & 1, q = (cta >> 1) & 3, jp = cta >> 3, head = 2 * jp + rank;
  const unsigned ep = *(volatile unsigned*)(smem + SM_RT + 4);
  bar_sync<NB_KV, NTHR>();
  TS(2);
  if (hw == 1) {
    if (lane == 0) {
      mbar_wait(bars + B_KL * 8);
      mbar_wait_cl(bars + B_KV * 8);
      fence_async();
      asm volatile("cp.async.bulk.global.shared::cta.bulk_group [%0], [%1], 32768;\ncp.async.bulk.commit_group;\ncp.async.bulk.wait_group 0;"
                   ::"l"(g_KV + (head * 4 + q) * 2048), "r"(sb + SM_B0) : "memory");
      cnt_arrive(C_KV + head * 4 + q);
    }
  } else if (hw == 0) {
    if (lane == 0) {
#pragma unroll 1
      for (int b = 1; b < 4; b++) {
        const int qq = (q + b) & 3;
        cnt_wait(C_KV + head * 4 + qq, ep, 1);
        fence_async_g();
        const uint32_t bar = bars + (B_KV + b) * 8, dst = sb + (b - 1) * BLK;
        mbar_expect(bar, 32768);
        bulk_g2s(dst, g_KV + (head * 4 + qq) * 2048, 32768, bar);
      }
      TS(3);
    }
  } else {
    const uint4 one = make_uint4(0x3F803F80u, 0x3F803F80u, 0x3F803F80u, 0x3F803F80u);
#pragma unroll 1
    for (int b = 1; b < 4; b++) {
#pragma unroll
      for (int i = 0; i < 8; i++) *(uint4*)(smem + (b - 1) * BLK + 32768 + (i * 64 + l - 64) * 16) = one;
      fence_async();
      __syncwarp();
      if (lane == 0) mbar_arrive(bars + (B_KV + b) * 8);
    }
  }
  __syncwarp();
  if (lane == 0) { mbar_wait(bars + (B_SO + hw * 2) * 8); cnt_arrive(C_O + ((q * 8 + rank * 4 + hw) * 2 + rank) * 4 + (jp >> 2)); }
  __syncwarp();
  if (l == 0) {
    mbar_wait(bars + B_QX * 8);
    mbar_expect(bars + B_WO * 8, 65536);
    tma2(sb + SM_WO0, &P.mo, (cta & 7) * 64, 0, bars + B_WO * 8);
    tma2(sb + SM_WO1, &P.mo, (cta & 7) * 64, 256, bars + B_WO * 8);
  }
  if (hw == 1) {
    if (lane == 0) cnt_wait(C_MOE, ep, NMOE);
    __syncwarp();
    const float2 route = __ldcg(&g_route);
    float y0 = 0.f, y1 = 0.f;
#pragma unroll
    for (int s = 0; s < NMOE; s++) { const float2 yp = __ldcg((const float2*)&g_ypart[s * D_ + (cta & 7) * 64 + 2 * lane]); y0 += yp.x; y1 += yp.y; }
    *(float2*)(smem + SM_RT + 16 + lane * 8) = make_float2(rbf(rbf(y0) * route.y), rbf(rbf(y1) * route.y));
    if (lane == 0) *(float*)(smem + SM_RT) = route.x;
    __syncwarp();
    if (lane == 0) mbar_arrive(bars + B_WO * 8);
  }
  if (hw >= 2) {
    const int rb = (jp >> 2) * 8 + (hw & 1) * 4 + (jp & 3);
    if (lane < 4) cnt_wait(C_O + (rb * 2 + (hw & 1)) * 4 + lane, ep, 4);
    __syncwarp();
    if (lane == 0) mbar_arrive(bars + B_EARLY * 8);
  }
  if (lane == 0) { mbar_wait(bars + (B_SO + hw * 2 + 1) * 8); cnt_arrive(C_O + ((q * 8 + (rank ^ 1) * 4 + hw) * 2 + rank) * 4 + (jp >> 2)); }
}

__device__ __forceinline__ void compute_wg(const Params& P, uint8_t* smem, int cta) {
  const int tid = threadIdx.x, lane = tid & 31, warp = tid >> 5, wg = tid >> 7, wi = warp & 3, t128 = tid & 127;
  const int g = lane >> 2, t = lane & 3;
  const uint32_t sb = (uint32_t)__cvta_generic_to_shared(smem), bars = sb + SM_BAR;
  const int rank = cta & 1, q = (cta >> 1) & 3, jp = cta >> 3;
  uint32_t qown[4];

  {
    if (lane == 0 && warp > 0) {
      const int i0 = warp + 3;
      if (i0 < B_KL) *(unsigned*)(smem + SM_BAR + i0 * 8) = 0;
      else mbar_init(bars + i0 * 8, i0 > B_KV && i0 < B_WO ? 3 : i0 == B_WO || i0 == B_EARLY ? 2 : i0 == B_QX || i0 == B_KL ? 16 : 1);
      if (warp < 13) mbar_init(bars + (18 + warp) * 8, 1);
      if (warp < 9) mbar_init(bars + (B_SO - 1 + warp) * 8, 4);
      if (warp == 13) mbar_init(bars + B_STG * 8, 4);
      if (warp == 14) { mbar_init(bars + B_QR * 8, 1); mbar_expect(bars + B_QR * 8, 8192); }
      if (i0 == B_KV) mbar_expect(bars + B_KV * 8, 16384);
      asm volatile("fence.mbarrier_init.release.cluster;" ::: "memory");
    }
    *(uint4*)(smem + SM_B0 + 32768 + tid * 16) = make_uint4(0x3F803F80u, 0x3F803F80u, 0x3F803F80u, 0x3F803F80u);
    if (wg == 3) {
      uint4 v = make_uint4(0, 0, 0, 0);
      if (((tid >> 3) & 1) == 0) {
        const bool mu = is_mu(t128 >> 4);
        const float sg = mu ? TWO_P71 : TWO_M71;
        const float c1 = mu ? -0.00292f : 126.0f, c2 = mu ? 0.f : 53.0f / 128.0f;
        v.x = packbf(sg, sg); v.y = packbf(sg, c1 * sg); v.z = packbf(c2 * sg, 0.f);
      }
      *(uint4*)(smem + SM_BIAS + t128 * 16) = v;
    }
    fence_async();
    bar_sync<0, NTHR>();
    asm volatile("barrier.cluster.arrive.relaxed.aligned;" ::: "memory");
    TS(21);
    float acc[48];
#pragma unroll
    for (int i = 0; i < 48; i++) acc[i] = 0.f;
    pin(acc);
    const uint64_t dA = mkdesc(sb + __shfl_sync(0xffffffffu, wg, 0) * 8192, 16, 1024, 1), dB = mkdesc(sb + 32768, 4096, 512, 2);
#pragma unroll
    for (int c = 0; c < 8; c++) {
      mbar_wait(bars + (B_FULL + c % 3) * 8, (c / 3) & 1);
      if (c == 0) TS(1);
      if (c == 1) TS(22);
      if (c == 3) TS(23);
      wg_fence();
#pragma unroll
      for (int ks = 0; ks < 4; ks++) wgmma_n96_ss_t<1>(acc, dA + (c % 3) * (STAGE / 16) + ks * 2, dB + (c % 3) * (STAGE / 16) + ks * 64);
      wg_commit();
      if (c < 5) {
        wg_wait<0>();
        if (t128 == 0) {
          unsigned old;
          asm volatile("atom.acq_rel.cta.shared.add.u32 %0, [%1], 1;" : "=r"(old) : "r"(bars + (B_REL + c % 3) * 8) : "memory");
          if ((old & 3) == 3) load_stage(P, sb, cta, c + 3, c % 3);
        }
      }
    }
    asm volatile("setmaxnreg.inc.sync.aligned.u32 112;");
    wg_wait<0>();
    pin(acc);
    TS(2);
    mbar_wait(bars + B_STG * 8);
    asm volatile("barrier.cluster.wait.aligned;" ::: "memory");
    TS(3);
    const int lr = wg * 64 + wi * 16 + g;
    const float2 st0 = ((const float2*)(smem + SM_ST))[lr], st1 = ((const float2*)(smem + SM_ST))[lr + 8];
    const float ks0 = is_mu(2 * wi) ? TWO_P71 : TWO_M71, ks1 = is_mu(2 * wi + 1) ? TWO_P71 : TWO_M71;
    auto frag = [&](int ng0, float c0, float c1, uint32_t* pk) {
      const float sc0 = st0.y * c0, sc1 = st1.y * c1;
#pragma unroll
      for (int hf = 0; hf < 2; hf++) {
        const int ng = ng0 + hf;
        const float2 cs = *(const float2*)(smem + SM_CS + (ng * 8 + 2 * t) * 4);
        pk[2 * hf] = packbf(fmaf(-st0.x, cs.x, acc[4 * ng]) * sc0, fmaf(-st0.x, cs.y, acc[4 * ng + 1]) * sc0);
        pk[2 * hf + 1] = packbf(fmaf(-st1.x, cs.x, acc[4 * ng + 2]) * sc1, fmaf(-st1.x, cs.y, acc[4 * ng + 3]) * sc1);
      }
    };
    const uint32_t rs = mapa(sb, rank ^ 1), rbar = rs + SM_BAR + B_KV * 8;
    const uint32_t kr = rs + SM_B0 + 8192 + wg * 2048 + wi * 512 + lane * 4, vr = rs + SM_B0 + 16384 + 4096 + wg * 1024 + wi * 256 + lane * 4;
    const uint32_t kl = sb + SM_B0 + wg * 2048 + (2 * wi + ((lane >> 3) & 1)) * 256 + (lane >> 4) * 128 + (lane & 7) * 16;
    const uint32_t vl = sb + SM_B0 + 16384 + (lane >> 4) * 8192 + wg * 1024 + (2 * wi + ((lane >> 3) & 1)) * 128 + (lane & 7) * 16;
    auto scatter = [&](int own, int oth) {
      uint32_t pk[4];
      frag(4 + oth, ks0, ks1, pk);
      st_async(kr, pk[0], rbar); st_async(kr + 256, pk[1], rbar); st_async(kr + 128, pk[2], rbar); st_async(kr + 384, pk[3], rbar);
      frag(8 + oth, 1.0f, 1.0f, pk);
      st_async(vr, pk[0], rbar); st_async(vr + 128, pk[1], rbar); st_async(vr + 8192, pk[2], rbar); st_async(vr + 8192 + 128, pk[3], rbar);
      frag(4 + own, ks0, ks1, pk);
      stsm4(kl, pk);
      frag(8 + own, 1.0f, 1.0f, pk);
      stsm4(vl, pk);
      frag(own, QSCALE * TWO_M71, QSCALE * TWO_M71, qown);
      frag(oth, QSCALE * TWO_M71, QSCALE * TWO_M71, pk);
      st_async4(rs + SM_QX + tid * 16, pk, rs + SM_BAR + B_QR * 8);
    };
    if (rank) scatter(2, 0); else scatter(0, 2);
    fence_async();
    __syncwarp();
    if (lane == 0) mbar_arrive(bars + B_KL * 8);
    bar_arrive<NB_KV, NTHR>();
  }
  TS(4);

  {
    Attn A;
    A.hexp = 0x3F003F00u;
    asm volatile("ld.shared.u32 %0, [%1];" : "=r"(A.neg1) : "r"(sb + SM_BIAS + 128));
    A.neg1 = ~A.neg1;
    const uint64_t dK = mkdesc(sb, 128, 256), dV = mkdesc(sb + 16384, 128, 8192);
    A.q[0] = qown[0]; A.q[1] = qown[1]; A.q[2] = qown[2]; A.q[3] = qown[3];
    mbar_wait(bars + B_KL * 8);
    TS(6); TSG(28);
    int first = 0;
#pragma unroll 1
    for (int r = 0; r < 2; r++) {
#pragma unroll 1
      for (int attempt = first; attempt < 3; attempt++) {
        const bool rowm = attempt != 0;
        float mM0 = -INFINITY, mM1 = -INFINITY, mP0 = -INFINITY, mP1 = -INFINITY;
#pragma unroll 1
        for (int tl = attempt == 2 ? 31 : 0; tl >= 0; tl--) {
          pin(A.s);
          wg_fence();
          wgmma_n64_k<0>(A.s, A.q[0], A.q[1], A.q[2], A.q[3], dK + (blk_off(tl >> 3) >> 4) + (tl & 7) * 128);
          wg_commit();
          wg_wait<0>();
          pin(A.s);
          if (!rowm) break;
#pragma unroll
          for (int blk = 0; blk < 8; blk++) {
            const float a0 = fmaxf(A.s[4 * blk], A.s[4 * blk + 1]), a1 = fmaxf(A.s[4 * blk + 2], A.s[4 * blk + 3]);
            if (is_mu(blk)) { mM0 = fmaxf(mM0, a0); mM1 = fmaxf(mM1, a1); }
            else { mP0 = fmaxf(mP0, a0); mP1 = fmaxf(mP1, a1); }
          }
        }
#pragma unroll
        for (int i = 0; i < 12; i++) A.o[i] = 0.f;
        if (r == 0) { mbar_wait_cl(bars + B_KV * 8); fence_async(); TS(5); }
        pin(A.o); pin(A.s);
        if (!rowm) {
          A.run(dK, dV, bars);
        } else {
          float m0 = fmaxf(mM0, mP0 * TWO_P71 * TWO_P71), m1 = fmaxf(mM1, mP1 * TWO_P71 * TWO_P71);
#pragma unroll
          for (int o = 1; o < 4; o <<= 1) {
            m0 = fmaxf(m0, __shfl_xor_sync(0xffffffffu, m0, o));
            m1 = fmaxf(m1, __shfl_xor_sync(0xffffffffu, m1, o));
          }
          m0 = -(ceilf(m0) + M_SHIFT); m1 = -(ceilf(m1) + M_SHIFT);
          const int t = fresh_tid() & 3;
          const float h0 = rbf(m0), i0 = rbf(m0 - h0), l0 = m0 - h0 - i0;
          const float h1 = rbf(m1), i1 = rbf(m1 - h1), l1 = m1 - h1 - i1;
          const float x0 = t == 0 ? h0 : t == 1 ? l0 : t == 2 ? 1.0f : 0.f, y0 = t == 0 ? i0 : t == 1 ? 1.0f : 0.f;
          const float x1 = t == 0 ? h1 : t == 1 ? l1 : t == 2 ? 1.0f : 0.f, y1 = t == 0 ? i1 : t == 1 ? 1.0f : 0.f;
          const uint32_t bq[4] = {packbf(x0 * TWO_M71, y0 * TWO_M71), packbf(x1 * TWO_M71, y1 * TWO_M71), ~A.neg1, ~A.neg1};
          A.run_rowm(dK, dV, bars, bq, mkdesc(sb + SM_BIAS, 128, 256));
        }
        bool bad = !(A.o[8] >= 4.9303806576313238e-32f) || !(A.o[10] >= 4.9303806576313238e-32f);
        float amax = fmaxf(A.o[8], A.o[10]);
#pragma unroll
        for (int i = 0; i < 8; i++) { bad = bad || (A.o[i] != A.o[i]); amax = fmaxf(amax, fabsf(A.o[i])); }
        bad = bad || !(amax <= 3.0e38f);
        if (!__any_sync(0xffffffffu, wg_any(fresh_tid() >> 7, bad))) break;
        first = 1;
        TSV(13, 1 + r);
      }
      const int tid = fresh_tid(), wg = tid >> 7, t128 = tid & 127, lane = tid & 31;
      const float c0 = A.o[8] > 1.0f ? 0.00390625f : 1.0f, c1 = A.o[10] > 1.0f ? 0.00390625f : 1.0f;
      const float i0 = rcp(A.o[8] * c0), i1 = rcp(A.o[10] * c1);
      g_O[((q * 8 + (rank ^ r) * 4 + wg) * 32 + rank * 16 + jp) * 128 + t128] =
          make_uint4(packbf(A.o[0] * c0 * i0, A.o[1] * c0 * i0), packbf(A.o[2] * c1 * i1, A.o[3] * c1 * i1),
                     packbf(A.o[4] * c0 * i0, A.o[5] * c0 * i0), packbf(A.o[6] * c1 * i1, A.o[7] * c1 * i1));
      __syncwarp();
      if (lane == 0) mbar_arrive(bars + (B_SO + wg * 2 + r) * 8);
      if (r == 0) {
        mbar_wait_cl(bars + B_QR * 8);
        const uint4 qn = *(const uint4*)(smem + SM_QX + tid * 16);
        A.q[0] = qn.x; A.q[1] = qn.y; A.q[2] = qn.z; A.q[3] = qn.w;
        asm volatile("" : "+r"(A.q[0]), "+r"(A.q[1]), "+r"(A.q[2]), "+r"(A.q[3])::"memory");
        __syncwarp();
        if (lane == 0) mbar_arrive(bars + B_QX * 8);
      }
      TS(7 + r); TSG(29 + r);
    }
  }

  {
    const int tid = fresh_tid(), wg = tid >> 7, t128 = tid & 127, wi = (tid >> 5) & 3, g = (tid >> 2) & 7, t = tid & 3;
    const int cb = cta & 7, late = wg < 2, tile = wg & 1;
    const int rb = (jp >> 2) * 8 + tile * 4 + (jp & 3), par = tile ^ late;
    const int R0 = rb * 64 + wi * 16 + g;
    const int aoff = wg == 3 ? SM_B0 : wg * 32768, eoff = tile ? SM_B0 : 65536;
    const unsigned ep = *(volatile unsigned*)(smem + SM_RT + 4);
    float4* ex = (float4*)(smem + eoff);
    const uint32_t wsel = __shfl_sync(0xffffffffu, par * 2048, 0);
    float acc[32];
    if (!late) {
      bar_arrive<NB_DONE, 512>();
      mbar_wait(bars + B_EARLY * 8);
      uint4 xq[4];
#pragma unroll
      for (int i = 0; i < 4; i++) xq[i] = __ldg((const uint4*)(P.x + (R0 + (i & 1) * 8) * D_ + cb * 64 + (i >> 1) * 32 + t * 8));
      const uint2 sw0 = __ldcg(&g_stats[R0]), sw1 = __ldcg(&g_stats[R0 + 8]);
      const uint4* go = &g_O[(rb * 32 + par * 16) * 128 + t128];
      uint4 ae[2][4];
#pragma unroll
      for (int h = 0; h < EPRE; h++) ae[h >> 2][h & 3] = ldg_cg(go + h * 128);
      float2 st[2] = {unpack_stats(sw0.x), unpack_stats(sw1.x)};
      if (sw0.y != ep + 1 || sw1.y != ep + 1) { st[0] = unpack_stats(ll_get(&g_stats[R0], ep)); st[1] = unpack_stats(ll_get(&g_stats[R0 + 8], ep)); }
      __syncwarp();
#pragma unroll
      for (int i = 0; i < 4; i++) {
        uint32_t v[4] = {xq[i].x, xq[i].y, xq[i].z, xq[i].w};
        quad_transpose(v, t);
#pragma unroll
        for (int b = 0; b < 4; b++) {
          const uint32_t d = packbf(bflo(v[b]) - st[i & 1].x, bfhi(v[b]) - st[i & 1].x);
          const uint32_t n = packbf(bflo(d) * st[i & 1].y, bfhi(d) * st[i & 1].y);
          acc[16 * (i >> 1) + 4 * b + 2 * (i & 1)] = bflo(v[b]) + bflo(n);
          acc[16 * (i >> 1) + 4 * b + 2 * (i & 1) + 1] = bfhi(v[b]) + bfhi(n);
        }
      }
      mbar_wait(bars + B_WO * 8);
      const int idx = *(const int*)(smem + SM_RT);
      if (R0 == (idx & ~8)) {
#pragma unroll
        for (int b = 0; b < 8; b++) {
          const float2 y = *(const float2*)(smem + SM_RT + 16 + (2 * t + b * 8) * 4);
          if (idx & 8) { acc[4 * b + 2] += y.x; acc[4 * b + 3] += y.y; } else { acc[4 * b] += y.x; acc[4 * b + 1] += y.y; }
        }
      }
#pragma unroll
      for (int h = EPRE; h < 8; h++) ae[h >> 2][h & 3] = ldg_cg(go + h * 128);
      TS(9);
      pin(acc);
#pragma unroll
      for (int q4 = 0; q4 < 4; q4++) {
        const uint64_t dW = mkdesc(sb + (q4 >= 2 ? SM_WO1 : SM_WO0) + wsel, 16, 1024, 1);
#pragma unroll
        for (int h = 0; h < 4; h++) { uint4& a = ae[q4 & 1][h]; asm volatile("" : "+r"(a.x), "+r"(a.y), "+r"(a.z), "+r"(a.w)::"memory"); }
        wg_fence();
#pragma unroll
        for (int h = 0; h < 4; h++) {
          const uint4& a = ae[q4 & 1][h];
          wgmma_n64_t<1>(acc, a.x, a.y, a.z, a.w, dW + ((q4 & 1) * 4 + h) * 256);
        }
        wg_commit();
        if (q4 < 2) {
          wg_wait<0>();
#pragma unroll
          for (int h = 0; h < 4; h++) ae[q4][h] = ldg_cg(go + (8 + q4 * 4 + h) * 128);
        }
      }
      wg_wait<0>();
      pin(acc);
      TS(10);
      mbar_wait(bars + B_DONE * 8);
#pragma unroll
      for (int b = 0; b < 8; b++) ex[b * 128 + t128] = make_float4(acc[4 * b], acc[4 * b + 1], acc[4 * b + 2], acc[4 * b + 3]);
      asm volatile("bar.arrive %0, 256;" ::"r"(tile + 5) : "memory");
    } else {
      bar_sync<NB_DONE, 512>();
      if (tid == 32) mbar_arrive(bars + B_DONE * 8);
      if (t128 < 4) {
        const unsigned* cnt = &g_cnt[(C_O + (rb * 2 + par) * 4 + t128) * 32];
        const uint32_t bar = bars + (B_O + wg * 4 + t128) * 8;
        bool done = false;
#pragma unroll 1
        for (int i = 0; i < (1 << 17) && !done; i++) {
          unsigned v;
          asm volatile("ld.relaxed.gpu.global.u32 %0, [%1];" : "=r"(v) : "l"(cnt) : "memory");
          if ((int)(v - (ep + 1) * 4) >= 0 || i == (1 << 17) - 1) {
            asm volatile("fence.acquire.gpu;" ::: "memory");
            fence_async_g();
            mbar_expect(bar, 8192);
            bulk_g2s(sb + aoff + t128 * 8192, &g_O[(rb * 32 + par * 16 + t128 * 4) * 128], 8192, bar);
            done = true;
          }
        }
      }
      __syncwarp();
#pragma unroll
      for (int i = 0; i < 32; i++) acc[i] = 0.f;
      mbar_wait(bars + B_WO * 8);
      TS(9);
      pin(acc);
      uint4 af[2][4];
#pragma unroll
      for (int q4 = 0; q4 < 4; q4++) {
        const uint64_t dW = mkdesc(sb + (q4 >= 2 ? SM_WO1 : SM_WO0) + wsel, 16, 1024, 1);
        mbar_wait(bars + (B_O + wg * 4 + q4) * 8);
        if (q4 >= 2) wg_wait<1>();
#pragma unroll
        for (int h = 0; h < 4; h++) {
          uint4& a = af[q4 & 1][h];
          a = *(const uint4*)(smem + aoff + ((q4 * 4 + h) * 128 + t128) * 16);
          asm volatile("" : "+r"(a.x), "+r"(a.y), "+r"(a.z), "+r"(a.w)::"memory");
        }
        wg_fence();
#pragma unroll
        for (int h = 0; h < 4; h++) {
          const uint4& a = af[q4 & 1][h];
          wgmma_n64_t<1>(acc, a.x, a.y, a.z, a.w, dW + ((q4 & 1) * 4 + h) * 256);
        }
        wg_commit();
      }
      wg_wait<0>();
      pin(acc);
      TS(10);
      bar_pair(tile);
#pragma unroll
      for (int hf = 0; hf < 2; hf++) {
        uint32_t o0[4], o1[4];
#pragma unroll
        for (int b = 0; b < 4; b++) {
          const float4 e = ex[(hf * 4 + b) * 128 + t128];
          o0[b] = packbf(acc[16 * hf + 4 * b] + e.x, acc[16 * hf + 4 * b + 1] + e.y);
          o1[b] = packbf(acc[16 * hf + 4 * b + 2] + e.z, acc[16 * hf + 4 * b + 3] + e.w);
        }
        quad_transpose(o0, t); quad_transpose(o1, t);
        __nv_bfloat16* po = P.out + R0 * D_ + cb * 64 + hf * 32 + t * 8;
        *(uint4*)po = make_uint4(o0[0], o0[1], o0[2], o0[3]);
        *(uint4*)(po + 8 * D_) = make_uint4(o1[0], o1[1], o1[2], o1[3]);
      }
    }
  }
}

__global__ void __cluster_dims__(2, 1, 1) __launch_bounds__(NTHR, 1) fused_kernel(const __grid_constant__ Params P) {
  extern __shared__ __align__(1024) uint8_t smem[];
  TS(0); TSG(14);
  if (threadIdx.x == 0 && blockIdx.x < NMAIN) {
    const uint32_t sb = (uint32_t)__cvta_generic_to_shared(smem);
    mbar_init(sb + SM_BAR, 1);
    asm volatile("fence.mbarrier_init.release.cluster;" ::: "memory");
    load_stage(P, sb, blockIdx.x, 0, 0);
    TS(17);
#pragma unroll
    for (int c = 1; c < 4; c++) mbar_init(sb + SM_BAR + c * 8, 1);
    asm volatile("fence.mbarrier_init.release.cluster;" ::: "memory");
    load_stage(P, sb, blockIdx.x, 1, 1);
    const uint32_t bar = sb + SM_BAR + B_CS * 8;
    mbar_expect(bar, blockIdx.x < 96 ? 16384 : 0);
    if (blockIdx.x < 96) {
      tma2(sb + SM_WC, &P.mc, blockIdx.x * 16, 0, bar);
      tma2(sb + SM_WC + 8192, &P.mc, blockIdx.x * 16, 256, bar);
    }
    load_stage(P, sb, blockIdx.x, 2, 2);
    TS(16);
  }
  if (blockIdx.x >= NMAIN) {
    if (threadIdx.x < 512) moe_cta(P, smem, blockIdx.x - NMAIN);
  } else if (threadIdx.x >= 512) {
    helper_wg(P, smem, blockIdx.x);
    helper_wg2(P, smem, blockIdx.x);
  } else {
    compute_wg(P, smem, blockIdx.x);
  }
  TS(11); TSG(15);
}

}

extern "C" void kernel_launch(void* const* d_in, const int* in_sizes, int n_in, void* d_out, int out_size) {
  (void)in_sizes; (void)n_in; (void)out_size;
  Params P = {};
  P.x = (const __nv_bfloat16*)d_in[0];
  P.wr = (const __nv_bfloat16*)d_in[4];
  P.wg = (const __nv_bfloat16*)d_in[5];
  P.wu = (const __nv_bfloat16*)d_in[6];
  P.wd = (const __nv_bfloat16*)d_in[7];
  P.out = (__nv_bfloat16*)d_out;
  typedef CUresult (*EncFn)(CUtensorMap*, CUtensorMapDataType, cuuint32_t, void*, const cuuint64_t*, const cuuint64_t*, const cuuint32_t*,
                            const cuuint32_t*, CUtensorMapInterleave, CUtensorMapSwizzle, CUtensorMapL2promotion, CUtensorMapFloatOOBfill);
  void* fn = nullptr;
  cudaDriverEntryPointQueryResult qr;
  cudaGetDriverEntryPoint("cuTensorMapEncodeTiled", &fn, cudaEnableDefault, &qr);
  const EncFn enc = (EncFn)fn;
  const cuuint32_t es[3] = {1, 1, 1};
  {
    const cuuint64_t gd[2] = {D_, S_}, gs[1] = {D_ * 2};
    const cuuint32_t box[2] = {64, 256};
    enc(&P.mx, CU_TENSOR_MAP_DATA_TYPE_BFLOAT16, 2, d_in[0], gd, gs, box, es, CU_TENSOR_MAP_INTERLEAVE_NONE, CU_TENSOR_MAP_SWIZZLE_128B,
        CU_TENSOR_MAP_L2_PROMOTION_L2_128B, CU_TENSOR_MAP_FLOAT_OOB_FILL_NONE);
  }
  {
    const cuuint64_t gd[3] = {D_, D_, 3}, gs[2] = {3 * D_ * 2, D_ * 2};
    const cuuint32_t box[3] = {32, 64, 3};
    enc(&P.mw, CU_TENSOR_MAP_DATA_TYPE_BFLOAT16, 3, d_in[1], gd, gs, box, es, CU_TENSOR_MAP_INTERLEAVE_NONE, CU_TENSOR_MAP_SWIZZLE_64B,
        CU_TENSOR_MAP_L2_PROMOTION_L2_128B, CU_TENSOR_MAP_FLOAT_OOB_FILL_NONE);
  }
  {
    const cuuint64_t gd[2] = {3 * D_, D_}, gs[1] = {3 * D_ * 2};
    const cuuint32_t box[2] = {16, 256};
    enc(&P.mc, CU_TENSOR_MAP_DATA_TYPE_BFLOAT16, 2, d_in[1], gd, gs, box, es, CU_TENSOR_MAP_INTERLEAVE_NONE, CU_TENSOR_MAP_SWIZZLE_NONE,
        CU_TENSOR_MAP_L2_PROMOTION_L2_128B, CU_TENSOR_MAP_FLOAT_OOB_FILL_NONE);
  }
  {
    const cuuint64_t gd[2] = {D_, D_}, gs[1] = {D_ * 2};
    const cuuint32_t box[2] = {64, 256};
    enc(&P.mo, CU_TENSOR_MAP_DATA_TYPE_BFLOAT16, 2, d_in[2], gd, gs, box, es, CU_TENSOR_MAP_INTERLEAVE_NONE, CU_TENSOR_MAP_SWIZZLE_128B,
        CU_TENSOR_MAP_L2_PROMOTION_L2_128B, CU_TENSOR_MAP_FLOAT_OOB_FILL_NONE);
  }
  cudaFuncSetAttribute(fused_kernel, cudaFuncAttributeMaxDynamicSharedMemorySize, SM_TOTAL);
  fused_kernel<<<NCTA, NTHR, SM_TOTAL>>>(P);
}
```
